```python
import torch

def _softmax(x, axis=-1):
    return torch.softmax(x, dim=axis)
def _gelu(x):
    return torch.nn.functional.gelu(x, approximate="tanh")
def _silu(x):
    return torch.nn.functional.silu(x)
def _sigmoid(x):
    return torch.sigmoid(x)
def _layernorm(x, axis=-1, eps=1e-5):
    m = x.mean(dim=axis, keepdim=True)
    v = x.var(dim=axis, keepdim=True, unbiased=False)
    return (x - m) / torch.sqrt(v + eps)
def _scatter_add(tgt, idx, src, axis=0):
    return tgt.clone().index_add_(axis, idx, src)
def _segment_sum(src, seg, n):
    out = torch.zeros((n,) + src.shape[1:], dtype=src.dtype)
    return out.index_add_(0, seg, src)
def _pad(x, pw):
    flat = tuple(v for pair in reversed(pw) for v in pair)
    return torch.nn.functional.pad(x, flat)

kernel_name = 'gated_mix__ssm_conv_s4d__ssm_conv_s5__prompt'

def setup_inputs():

    _w = (lambda a: (lambda t: t.to(torch.bfloat16) if t.is_floating_point() else t)(torch.as_tensor(a)))
    def _A_setup():
        Bsz, L, D, N = 1, 2048, 448, 256
        return {
            "u": _w((lambda *s: torch.randn(*s, dtype=torch.bfloat16) * 0.05)(Bsz, L, D)),
            "log_A_real": _w((lambda *s: torch.randn(*s, dtype=torch.bfloat16) * 3.2)(D, N) * 0.5),
            "A_imag": _w((lambda *s: torch.randn(*s, dtype=torch.bfloat16) * 0.05)(D, N) * 3.14),
            "C_real": _w((lambda *s: torch.randn(*s, dtype=torch.bfloat16) * 0.1)(D, N) / N ** 0.5),
            "C_imag": _w((lambda *s: torch.randn(*s, dtype=torch.bfloat16) * 0.1)(D, N) / N ** 0.5),
            "log_dt": _w((lambda *s: torch.randn(*s, dtype=torch.bfloat16) * 0.05)(D) * 0.5 - 4.0),
            "D_skip": _w((lambda *s: torch.randn(*s, dtype=torch.bfloat16) * 0.05)(D)),
        }
    _A_in = _A_setup()

    def _B_setup():
        B, S, D = 1, 2048, 448
        P = D
        Lambda_re = -0.5 * (lambda _x: torch.exp(torch.as_tensor(_x)))((lambda *s: torch.randn(*s, dtype=torch.bfloat16) * 0.2)(P))
        Lambda_im = (lambda *s: torch.randn(*s, dtype=torch.bfloat16) * 0.4)(P) * 1.0
        B_re = (lambda *s: torch.randn(*s, dtype=torch.bfloat16) * 0.2)(P, D) * (D ** -0.5)
        B_im = (lambda *s: torch.randn(*s, dtype=torch.bfloat16) * 0.2)(P, D) * (D ** -0.5)
        C_re = (lambda *s: torch.randn(*s, dtype=torch.bfloat16) * 0.2)(D, P) * (P ** -0.5)
        C_im = (lambda *s: torch.randn(*s, dtype=torch.bfloat16) * 0.2)(D, P) * (P ** -0.5)
        log_dt = (lambda *s: torch.randn(*s, dtype=torch.bfloat16) * 0.2)(P) * 0.3 - 2.0
        Dskip = (lambda *s: torch.randn(*s, dtype=torch.bfloat16) * 0.05)(D)
        return {
            "x": _w((lambda *s: torch.randn(*s, dtype=torch.bfloat16) * 0.05)(B, S, D)),
            "Lambda_re": _w(Lambda_re),
            "Lambda_im": _w(Lambda_im),
            "B_re": _w(B_re),
            "B_im": _w(B_im),
            "C_re": _w(C_re),
            "C_im": _w(C_im),
            "log_dt": _w(log_dt),
            "Dskip": _w(Dskip),
        }
    _B_in = _B_setup()

    return {
        "A_u": _A_in["u"],
        "A_log_A_real": _A_in["log_A_real"],
        "A_A_imag": _A_in["A_imag"],
        "A_C_real": _A_in["C_real"],
        "A_C_imag": _A_in["C_imag"],
        "A_log_dt": _A_in["log_dt"],
        "A_D_skip": _A_in["D_skip"],
        "B_x": _B_in["x"],
        "B_Lambda_re": _B_in["Lambda_re"],
        "B_Lambda_im": _B_in["Lambda_im"],
        "B_B_re": _B_in["B_re"],
        "B_B_im": _B_in["B_im"],
        "B_C_re": _B_in["C_re"],
        "B_C_im": _B_in["C_im"],
        "B_log_dt": _B_in["log_dt"],
        "B_Dskip": _B_in["Dskip"],
        "gate_w": _w((lambda *s: torch.randn(*s, dtype=torch.bfloat16) * 0.05)(448) * 16.0),
    }

def reference(A_u, A_log_A_real, A_A_imag, A_C_real, A_C_imag, A_log_dt, A_D_skip, B_x, B_Lambda_re, B_Lambda_im, B_B_re, B_B_im, B_C_re, B_C_im, B_log_dt, B_Dskip, gate_w):
    def _A_ref(u, log_A_real, A_imag, C_real, C_imag, log_dt, D_skip):
        L = u.shape[1]
        dt = torch.exp(log_dt)
        A = -torch.exp(log_A_real) + 1j * A_imag
        C = (C_real + 1j * C_imag) * dt[:, None]
        pos = (lambda x, dt: x.to(dt))(torch.arange(L), log_dt.dtype)
        P = torch.exp((A * dt[:, None])[:, :, None] * pos[None, None, :])
        K = 2.0 * torch.einsum("dn,dnl->dl", C, P).real
        L2 = 2 * L
        u_t = (lambda x, *d: x.permute(*d))(u, 0, 2, 1)
        Kf = (lambda x, *a, **k: torch.fft.rfft(x.float(), *a, **k))(K, L2)
        Uf = (lambda x, *a, **k: torch.fft.rfft(x.float(), *a, **k))(u_t, L2)
        y = (lambda x, *a, **k: torch.fft.irfft(x, *a, **k).to(torch.bfloat16))(Uf * Kf[None, :, :], L2)[:, :, :L]
        y = (lambda x, *d: x.permute(*d))(y, 0, 2, 1)
        return y + u * D_skip[None, None, :]

    def _B_ref(x, Lambda_re, Lambda_im, B_re, B_im, C_re, C_im, log_dt, Dskip):
        Bsz, L, H = x.shape
        Lam = Lambda_re + 1j * Lambda_im
        Bmat = B_re + 1j * B_im
        Cmat = C_re + 1j * C_im
        dt = torch.exp(log_dt)
        Lam_bar = torch.exp(dt * Lam)
        B_bar = ((Lam_bar - 1.0) / Lam)[:, None] * Bmat
        Bu = torch.einsum("bld,pd->blp", x + 0j, B_bar)
        h = torch.zeros_like(Bu[:, 0, :])
        hs = []
        for t in range(L):
            h = Lam_bar[None, :] * h + Bu[:, t, :]
            hs.append(h)
        hseq = torch.stack(hs, 1)
        y = 2.0 * torch.einsum("blp,dp->bld", hseq, Cmat).real + x * Dskip[None, None, :]
        return y

    x = A_u
    g = _sigmoid((x * gate_w).sum(-1, keepdims=True))
    a = _A_ref(x, A_log_A_real, A_A_imag, A_C_real, A_C_imag, A_log_dt, A_D_skip)
    b = _B_ref(x, B_Lambda_re, B_Lambda_im, B_B_re, B_B_im, B_C_re, B_C_im, B_log_dt, B_Dskip)
    return g * a + (1 - g) * b
```

```cpp
#include <cuda_runtime.h>
#include <cuda_bf16.h>
#include <cuda_fp16.h>
#include <cuda.h>
#include <stdint.h>

namespace {

constexpr int kCTAs = 112;
constexpr int SLOT = 16384;
constexpr int OFF_TAB = 5 * SLOT;
constexpr int OFF_REG = 9 * SLOT;
constexpr int REG_SZ = 18432;
constexpr int OFF_GF = OFF_REG + 4 * REG_SZ;
constexpr int OFF_OMG = OFF_GF + 4096;
constexpr int OFF_XQ = OFF_OMG + 512;
constexpr int OFF_CST = OFF_GF;
constexpr int OFF_MISC = OFF_XQ + 6144;
constexpr int SMEM_TOTAL = OFF_MISC + 512;
constexpr int R_ULO = 0, R_UHI = 2240;
constexpr int R_A5 = 4416, R_A3 = 7552, HI_B = 1600;
constexpr int R_A9 = 10688, R_A7 = 12800, HI_S = 1088;
constexpr int R_KTAB = 4480;
constexpr int R_LAND = 12800;
constexpr int R_P = 14912;
constexpr int R_T53 = 17088;
constexpr int R_T97 = 17472;
constexpr int R_END = 18112, KT_BYTES = R_END - R_P + 1536;
constexpr int HELP_WG = 53248;
constexpr int OFF_DSK = OFF_MISC + 288, OFF_AD = OFF_DSK + 128, OFF_EP = OFF_AD + 8;
constexpr int B_STAGE = 0, B_CLATE = 7, B_FULLH = 8, B_LAND = 15, B_FULLA = 16, B_EMPTY4 = 17, B_CEARLY = 18, B_KT = 19, B_EMPTY1 = 20, B_GATE = 30, B_G1DONE = 31,
              B_UFULL = 23, B_XFREE = 24, B_REGFREE = 25, B_STEP0 = 26, B_REGFREE2 = 27, B_STEP1 = 28,
              B_HST = 32, B_HOUT = 34;
constexpr int NB_G1 = 11, NB_CONV = 12;
constexpr int SPIN_MAX = 1 << 20;
#define UDELAY 500
#define HOLD 3
#define KUNR 8
#define NP3 0
#define ABL 0
#define EVT 1
#define TDEL 0
#define KSTAG 0
#define CDEF 0
#define AWAIT 2
#define REPOLL 1
#define GLATE 1
#define HONE 1
#define SKIPD 1
enum { TM_X = 0, TM_B = 1, TM_C = 2, TM_U = 3, TM_A = 4 };
struct Maps { CUtensorMap m[5]; };

struct Params {
  const __nv_bfloat16* ap[4];
  const __nv_bfloat16* aldt;
  int nhelp;
  uint32_t zero;
  const __nv_bfloat16* adsk;
  const __nv_bfloat16* sv[5];
  const char* w[4];
  uint4 *agg, *h;
  uint2* gate;
  uint32_t *a, *hflag, *acnt, *epoch, *kflag;
  char* kt;
  const uint32_t* x;
  float* out;
  int bswap;
  int cswap;
};

__device__ uint4 g_agg[7 * 16 * 64];
__device__ __align__(128) uint2 g_gate[2048];
__device__ __align__(1024) uint4 g_h[16 * 7 * 2 * 1024];
__device__ __align__(1024) uint32_t g_a[16 * 448 * 64];
__device__ __align__(128) uint32_t g_hflag[16 * 8 * 16];
__device__ __align__(128) uint32_t g_acnt[7 * 32];
__device__ __align__(128) uint32_t g_kflag[kCTAs * 8];
__device__ __align__(128) char g_kt[kCTAs * KT_BYTES];
__device__ uint32_t g_epoch[kCTAs + 38 * 12];
#define TS(id) do {} while (0)
#define TX(id) do {} while (0)
#define TS4(id) do {} while (0)
#define TG(ph, st, k) do {} while (0)

__device__ __forceinline__ void mbar_init(uint32_t bar, uint32_t cnt) {
  asm volatile("mbarrier.init.shared::cta.b64 [%0], %1;" ::"r"(bar), "r"(cnt) : "memory");
}
__device__ __forceinline__ void mbar_expect(uint32_t bar, uint32_t bytes) {
  asm volatile("mbarrier.arrive.expect_tx.shared::cta.b64 _, [%0], %1;" ::"r"(bar), "r"(bytes) : "memory");
}
__device__ __forceinline__ void mbar_arrive(uint32_t bar) {
  asm volatile("mbarrier.arrive.shared::cta.b64 _, [%0];" ::"r"(bar) : "memory");
}
__device__ __forceinline__ void mbar_wait0(uint32_t bar) {
  asm volatile("{.reg .pred p; .reg .u32 n;\n"
               "mbarrier.try_wait.parity.shared::cta.b64 p, [%0], 0; @p bra.uni D; mov.u32 n, 0;\n"
               "W: mbarrier.try_wait.parity.shared::cta.b64 p, [%0], 0;\n"
               "add.u32 n, n, 1; setp.lt.and.u32 p, n, 1048576, !p; @p bra.uni W;\n"
               "D: }" ::"r"(bar) : "memory");
}
__device__ __forceinline__ void bar_arrive(int id, int n) { asm volatile("bar.arrive %0, %1;" ::"r"(id), "r"(n) : "memory"); }
__device__ __forceinline__ uint32_t ld16(const __nv_bfloat16* p) {
  uint32_t v;
  asm volatile("ld.global.nc.u16 %0, [%1];" : "=r"(v) : "l"(p));
  return v;
}
__device__ __forceinline__ uint32_t clock32() {
  uint32_t c;
  asm volatile("mov.u32 %0, %%clock;" : "=r"(c)::"memory");
  return c;
}
__device__ __forceinline__ void st_flag(uint32_t* p, uint32_t v) {
  asm volatile("st.relaxed.gpu.global.v4.u32 [%0], {%1,%1,%1,%1};" ::"l"(p), "r"(v) : "memory");
}
__device__ __forceinline__ bool elect() {
  uint32_t p;
  asm volatile("{.reg .pred P; elect.sync _|P, 0xffffffff; selp.u32 %0, 1, 0, P;}" : "=r"(p));
  return p;
}
__device__ __forceinline__ void bar_sync(int id, int n) { asm volatile("bar.sync %0, %1;" ::"r"(id), "r"(n) : "memory"); }
__device__ __forceinline__ void fence_async_smem() { asm volatile("fence.proxy.async.shared::cta;" ::: "memory"); }
__device__ __forceinline__ void tma5(uint32_t dst, const CUtensorMap* m, int c0, int c3, int c4, uint32_t bar) {
  asm volatile("cp.async.bulk.tensor.5d.shared::cluster.global.mbarrier::complete_tx::bytes [%0], [%1, {%3, %6, %6, %4, %5}], [%2];"
               ::"r"(dst), "l"(m), "r"(bar), "r"(c0), "r"(c3), "r"(c4), "r"(0) : "memory");
}
__device__ __forceinline__ void bulk_g2s(uint32_t dst, const void* src, uint32_t bytes, uint32_t bar) {
  asm volatile("cp.async.bulk.shared::cluster.global.mbarrier::complete_tx::bytes [%0], [%1], %2, [%3];"
               ::"r"(dst), "l"(src), "r"(bytes), "r"(bar) : "memory");
}
__device__ __forceinline__ void bulk_s2g(void* dst, uint32_t src, uint32_t bytes) {
  asm volatile("cp.async.bulk.global.shared::cta.bulk_group [%0], [%1], %2;" ::"l"(dst), "r"(src), "r"(bytes) : "memory");
}
__device__ __forceinline__ void wg_fence() { asm volatile("wgmma.fence.sync.aligned;" ::: "memory"); }
__device__ __forceinline__ void wg_commit() { asm volatile("wgmma.commit_group.sync.aligned;" ::: "memory"); }
template <int N> __device__ __forceinline__ void wg_wait() { asm volatile("wgmma.wait_group.sync.aligned %0;" ::"n"(N) : "memory"); }

#define ACC8(d, o) "+f"(d[o]), "+f"(d[o + 1]), "+f"(d[o + 2]), "+f"(d[o + 3]), "+f"(d[o + 4]), "+f"(d[o + 5]), "+f"(d[o + 6]), "+f"(d[o + 7])
#define REGS32 "%0,%1,%2,%3,%4,%5,%6,%7,%8,%9,%10,%11,%12,%13,%14,%15,%16,%17,%18,%19,%20,%21,%22,%23,%24,%25,%26,%27,%28,%29,%30,%31"
#define REGS64 REGS32 ",%32,%33,%34,%35,%36,%37,%38,%39,%40,%41,%42,%43,%44,%45,%46,%47,%48,%49,%50,%51,%52,%53,%54,%55,%56,%57,%58,%59,%60,%61,%62,%63"
__device__ __forceinline__ void wgmma_n128_ss(float (&d)[64], uint64_t da, uint64_t db, int acc) {
  asm volatile("{.reg .pred p; setp.ne.b32 p, %66, 0;\n"
               "wgmma.mma_async.sync.aligned.m64n128k16.f32.bf16.bf16 {" REGS64 "}, %64, %65, p, 1, 1, 0, 0;}"
               : ACC8(d, 0), ACC8(d, 8), ACC8(d, 16), ACC8(d, 24), ACC8(d, 32), ACC8(d, 40), ACC8(d, 48), ACC8(d, 56)
               : "l"(da), "l"(db), "r"(acc));
}
__device__ __forceinline__ void wgmma_n128_rs(float (&d)[64], uint32_t a0, uint32_t a1, uint32_t a2, uint32_t a3, uint64_t db, int acc) {
  asm volatile("{.reg .pred p; setp.ne.b32 p, %69, 0;\n"
               "wgmma.mma_async.sync.aligned.m64n128k16.f32.bf16.bf16 {" REGS64 "}, {%64,%65,%66,%67}, %68, p, 1, 1, 0;}"
               : ACC8(d, 0), ACC8(d, 8), ACC8(d, 16), ACC8(d, 24), ACC8(d, 32), ACC8(d, 40), ACC8(d, 48), ACC8(d, 56)
               : "r"(a0), "r"(a1), "r"(a2), "r"(a3), "l"(db), "r"(acc));
}
__device__ __forceinline__ void wgmma_n128_ss_tb(float (&d)[64], uint64_t da, uint64_t db) {
  asm volatile("wgmma.mma_async.sync.aligned.m64n128k16.f32.bf16.bf16 {" REGS64 "}, %64, %65, 1, 1, 1, 0, 1;"
               : ACC8(d, 0), ACC8(d, 8), ACC8(d, 16), ACC8(d, 24), ACC8(d, 32), ACC8(d, 40), ACC8(d, 48), ACC8(d, 56)
               : "l"(da), "l"(db));
}
__device__ __forceinline__ void mma_bf16_z(float* c, uint32_t a0, uint32_t a1, uint32_t a2, uint32_t a3, uint32_t b0, uint32_t b1) {
  asm volatile("mma.sync.aligned.m16n8k16.row.col.f32.bf16.bf16.f32 {%0,%1,%2,%3}, {%4,%5,%6,%7}, {%8,%9}, {%10,%10,%10,%10};"
               : "=f"(c[0]), "=f"(c[1]), "=f"(c[2]), "=f"(c[3]) : "r"(a0), "r"(a1), "r"(a2), "r"(a3), "r"(b0), "r"(b1), "f"(0.f));
}
__device__ __forceinline__ void mma_bf16(float* c, uint32_t a0, uint32_t a1, uint32_t a2, uint32_t a3, uint32_t b0, uint32_t b1) {
  asm volatile("mma.sync.aligned.m16n8k16.row.col.f32.bf16.bf16.f32 {%0,%1,%2,%3}, {%4,%5,%6,%7}, {%8,%9}, {%0,%1,%2,%3};"
               : "+f"(c[0]), "+f"(c[1]), "+f"(c[2]), "+f"(c[3]) : "r"(a0), "r"(a1), "r"(a2), "r"(a3), "r"(b0), "r"(b1));
}
__device__ __forceinline__ void mma_bf16_if(bool on, float* c, const uint32_t (&a)[4], uint2 b) {
  asm volatile("{.reg .pred p; setp.ne.u32 p, %10, 0;\n"
               "@p mma.sync.aligned.m16n8k16.row.col.f32.bf16.bf16.f32 {%0,%1,%2,%3}, {%4,%5,%6,%7}, {%8,%9}, {%0,%1,%2,%3};}"
               : "+f"(c[0]), "+f"(c[1]), "+f"(c[2]), "+f"(c[3]) : "r"(a[0]), "r"(a[1]), "r"(a[2]), "r"(a[3]), "r"(b.x), "r"(b.y), "r"((uint32_t)on));
}
__device__ __forceinline__ void mma_f16(float* c, uint32_t a0, uint32_t a1, uint32_t a2, uint32_t a3, uint32_t b0, uint32_t b1) {
  asm volatile("mma.sync.aligned.m16n8k16.row.col.f32.f16.f16.f32 {%0,%1,%2,%3}, {%4,%5,%6,%7}, {%8,%9}, {%0,%1,%2,%3};"
               : "+f"(c[0]), "+f"(c[1]), "+f"(c[2]), "+f"(c[3]) : "r"(a0), "r"(a1), "r"(a2), "r"(a3), "r"(b0), "r"(b1));
}
__device__ __forceinline__ void ldsm4(uint32_t a, uint32_t& r0, uint32_t& r1, uint32_t& r2, uint32_t& r3) {
  asm volatile("ldmatrix.sync.aligned.m8n8.x4.shared.b16 {%0,%1,%2,%3}, [%4];" : "=r"(r0), "=r"(r1), "=r"(r2), "=r"(r3) : "r"(a) : "memory");
}
__device__ __forceinline__ void ldsm4t(uint32_t a, uint32_t& r0, uint32_t& r1, uint32_t& r2, uint32_t& r3) {
  asm volatile("ldmatrix.sync.aligned.m8n8.x4.trans.shared.b16 {%0,%1,%2,%3}, [%4];" : "=r"(r0), "=r"(r1), "=r"(r2), "=r"(r3) : "r"(a) : "memory");
}
__device__ __forceinline__ void stsm4(uint32_t a, uint32_t r0, uint32_t r1, uint32_t r2, uint32_t r3) {
  asm volatile("stmatrix.sync.aligned.m8n8.x4.shared.b16 [%0], {%1,%2,%3,%4};" ::"r"(a), "r"(r0), "r"(r1), "r"(r2), "r"(r3) : "memory");
}
__device__ __forceinline__ uint32_t lds16(uint32_t a) { uint32_t v; asm volatile("ld.shared.u16 %0, [%1];" : "=r"(v) : "r"(a) : "memory"); return v; }
__device__ __forceinline__ uint32_t lds32(uint32_t a) { uint32_t v; asm volatile("ld.shared.u32 %0, [%1];" : "=r"(v) : "r"(a) : "memory"); return v; }
__device__ __forceinline__ uint2 lds64(uint32_t a) { uint2 v; asm volatile("ld.shared.v2.u32 {%0,%1}, [%2];" : "=r"(v.x), "=r"(v.y) : "r"(a) : "memory"); return v; }
__device__ __forceinline__ uint4 lds128(uint32_t a) { uint4 v; asm volatile("ld.shared.v4.u32 {%0,%1,%2,%3}, [%4];" : "=r"(v.x), "=r"(v.y), "=r"(v.z), "=r"(v.w) : "r"(a) : "memory"); return v; }
__device__ __forceinline__ void sts16(uint32_t a, uint32_t v) { asm volatile("{.reg .b16 l,h; mov.b32 {l,h}, %1; st.shared.u16 [%0], l;}" ::"r"(a), "r"(v) : "memory"); }
__device__ __forceinline__ void sts32(uint32_t a, uint32_t v) { asm volatile("st.shared.u32 [%0], %1;" ::"r"(a), "r"(v) : "memory"); }
__device__ __forceinline__ void sts64(uint32_t a, uint32_t x, uint32_t y) { asm volatile("st.shared.v2.u32 [%0], {%1,%2};" ::"r"(a), "r"(x), "r"(y) : "memory"); }
__device__ __forceinline__ void sts128(uint32_t a, uint32_t x, uint32_t y, uint32_t z, uint32_t w) {
  asm volatile("st.shared.v4.u32 [%0], {%1,%2,%3,%4};" ::"r"(a), "r"(x), "r"(y), "r"(z), "r"(w) : "memory");
}
__device__ __forceinline__ void sts16_if(bool c, uint32_t a, uint32_t v) { asm volatile("{.reg .pred p; .reg .b16 l,h; setp.ne.u32 p, %2, 0; mov.b32 {l,h}, %1; @p st.shared.u16 [%0], l;}" ::"r"(a), "r"(v), "r"((uint32_t)c) : "memory"); }
__device__ __forceinline__ void sts32_if(bool c, uint32_t a, uint32_t v) { asm volatile("{.reg .pred p; setp.ne.u32 p, %2, 0; @p st.shared.u32 [%0], %1;}" ::"r"(a), "r"(v), "r"((uint32_t)c) : "memory"); }
__device__ __forceinline__ void sts64_if(bool c, uint32_t a, uint32_t x, uint32_t y) { asm volatile("{.reg .pred p; setp.ne.u32 p, %3, 0; @p st.shared.v2.u32 [%0], {%1,%2};}" ::"r"(a), "r"(x), "r"(y), "r"((uint32_t)c) : "memory"); }
__device__ __forceinline__ void stsz_if(bool c, uint32_t a) { asm volatile("{.reg .pred p; setp.ne.u32 p, %1, 0; @p st.shared.v4.u32 [%0], {%2,%2,%2,%2};}" ::"r"(a), "r"((uint32_t)c), "r"(0u) : "memory"); }
__device__ __forceinline__ uint32_t pack_bf(float lo, float hi) { uint32_t d; asm("cvt.rn.bf16x2.f32 %0, %1, %2;" : "=r"(d) : "f"(hi), "f"(lo)); return d; }
__device__ __forceinline__ uint32_t pack_h(float lo, float hi) { uint32_t d; asm("cvt.rn.f16x2.f32 %0, %1, %2;" : "=r"(d) : "f"(hi), "f"(lo)); return d; }
__device__ __forceinline__ float bf_lo(uint32_t v) { return __uint_as_float(v << 16); }
__device__ __forceinline__ float bf_hi(uint32_t v) { return __uint_as_float(v & 0xffff0000u); }
__device__ __forceinline__ float bf_round(float x) { return bf_lo(pack_bf(x, 0.f)); }
__device__ __forceinline__ float ex2a(float x) { float y; asm("ex2.approx.ftz.f32 %0, %1;" : "=f"(y) : "f"(x)); return y; }
__device__ __forceinline__ uint32_t h2mul(uint32_t a, uint32_t b) { uint32_t d; asm("mul.rn.f16x2 %0, %1, %2;" : "=r"(d) : "r"(a), "r"(b)); return d; }
__device__ __forceinline__ uint32_t h2fma(uint32_t a, uint32_t b, uint32_t c) { uint32_t d; asm("fma.rn.f16x2 %0, %1, %2, %3;" : "=r"(d) : "r"(a), "r"(b), "r"(c)); return d; }
__device__ __forceinline__ uint32_t h2fms(uint32_t a, uint32_t b, uint32_t c) {
  uint32_t d; asm("{.reg .b32 n; neg.f16x2 n, %3; fma.rn.f16x2 %0, %1, %2, n;}" : "=r"(d) : "r"(a), "r"(b), "r"(c)); return d;
}

__device__ __forceinline__ uint32_t b2add(uint32_t a, uint32_t b) { uint32_t d; asm("add.rn.bf16x2 %0, %1, %2;" : "=r"(d) : "r"(a), "r"(b)); return d; }

struct Cx { float x, y; };
__device__ __forceinline__ Cx cmul(Cx a, Cx b) { return {fmaf(a.x, b.x, -a.y * b.y), fmaf(a.x, b.y, a.y * b.x)}; }
__device__ __forceinline__ Cx cfma(Cx a, Cx b, Cx c) { return {fmaf(a.x, b.x, fmaf(-a.y, b.y, c.x)), fmaf(a.x, b.y, fmaf(a.y, b.x, c.y))}; }
__device__ __forceinline__ float mul2(float a, float b) {
  float z;
  asm("{.reg .f32 t; mul.ftz.f32 t, %1, %2; mul.ftz.f32 %0, t, 0f40000000;}" : "=f"(z) : "f"(a), "f"(b));
  return z;
}
__device__ __forceinline__ Cx csqr(Cx a) { return {fmaf(a.x, a.x, -a.y * a.y), mul2(a.x, a.y)}; }
__device__ __forceinline__ Cx csqrc(Cx a) { return {fmaf(a.x, a.x, -a.y * a.y), mul2(-a.x, a.y)}; }
__device__ __forceinline__ Cx cexp_fast(float l2, float th) {
  const float m = ex2a(l2);
  return {m * __cosf(th), m * __sinf(th)};
}
struct H2 { uint32_t x, y; };
__device__ __forceinline__ H2 hmul(H2 a, H2 b) { return {h2fms(a.x, b.x, h2mul(a.y, b.y)), h2fma(a.x, b.y, h2mul(a.y, b.x))}; }
__device__ __forceinline__ H2 hpack(const Cx* v) { return {pack_h(v[0].x, v[1].x), pack_h(v[0].y, v[1].y)}; }
__device__ __forceinline__ uint64_t desc128(uint32_t a) { return 0x4000004000010000ull | (uint64_t)((a & 0x3FFFFu) >> 4); }

struct KIn { uint32_t lar, aim, cre, cim, ldt; };
__device__ __forceinline__ KIn kgen_load(const Params& p, uint32_t w, bool use) {
  KIn k = {0u, 0u, 0u, 0u, 0u};
  asm volatile("{.reg .pred p; setp.ne.u32 p, %10, 0;\n"
               "@p ld.relaxed.gpu.global.u32 %0, [%5]; @p ld.relaxed.gpu.global.u32 %1, [%6]; @p ld.relaxed.gpu.global.u16 %4, [%9];\n"
               "@p ld.relaxed.gpu.global.u32 %2, [%7]; @p ld.relaxed.gpu.global.u32 %3, [%8];\n"
               "@!p prefetch.global.L2 [%5]; @!p prefetch.global.L2 [%6]; @!p prefetch.global.L2 [%7]; @!p prefetch.global.L2 [%8];}"
               : "+r"(k.lar), "+r"(k.aim), "+r"(k.cre), "+r"(k.cim), "+r"(k.ldt)
               : "l"((const uint32_t*)p.ap[0] + w), "l"((const uint32_t*)p.ap[1] + w), "l"((const uint32_t*)p.ap[2] + w),
                 "l"((const uint32_t*)p.ap[3] + w), "l"(p.aldt + (w >> 7)), "r"((uint32_t)use));
  return k;
}
template <int UNR>
__device__ __forceinline__ void kgen(const KIn& in, uint32_t tab, int lane, uint32_t zero, uint32_t (&pk)[12], uint32_t delay = 0, int nb = 0) {
  float ka[6][4], unscale;
  const int g = lane >> 2, t = lane & 3;
  uint32_t ta = tab + lane * 256 + (((t << 1) | (g & 1)) << 4);
  uint32_t ca = tab + t * 256 + ((g ^ (2 * t)) << 4), cf = tab + t * 256 + 136 + ((7 ^ (2 * t)) << 4);
#pragma unroll
  for (int k = 0; k < 6; k++) { ka[k][0] = ka[k][1] = ka[k][2] = ka[k][3] = 0.f; }
  asm volatile("" : "+r"(ta), "+r"(ca), "+r"(cf));
  const uint32_t dep = clock32() & zero;
  const uint32_t plar = in.lar, paim = in.aim, pcre = in.cre, pcim = in.cim, rdt = in.ldt;
  const float dt = bf_round(expf(__uint_as_float(rdt << (16 + dep))));
  const uint32_t msk = 0x7f807f80u | dep, m0 = __vmaxu2(pcre & msk, pcim & msk);
  uint32_t mx = __reduce_max_sync(~0u, max(m0 & 0xffffu, m0 >> 16)) >> 7;
  mx = min(max(mx, 11u), 253u);
  const float cs = __uint_as_float((264u - mx) << 23);
  unscale = 2.0f * dt * __uint_as_float((mx - 10u) << 23);
  if (delay) {
    const uint32_t c0 = clock32() + (mx & zero);
    uint32_t d = 0;
    while (clock32() - c0 < delay + d) d = lds32(ca) & zero;
  }
  Cx v[2], u[2];
#pragma unroll
  for (int m = 0; m < 2; m++) {
    const float er = bf_round(ex2a((m ? bf_hi(plar | dep) : bf_lo(plar | dep)) * 1.4426950408889634f));
    const float l2 = (-er * dt) * 1.4426950408889634f;
    const float th = (m ? bf_hi(paim | dep) : bf_lo(paim | dep)) * dt;
    v[m] = cexp_fast(l2, th);
    u[m] = cexp_fast(64.f * l2, -64.f * th);
  }
#define SQ(a) a[0] = csqr(a[0]); a[1] = csqr(a[1]);
#define SQC(a) a[0] = csqrc(a[0]); a[1] = csqrc(a[1]);
  const H2 cc = {pack_h(bf_lo(pcre | dep) * cs, bf_hi(pcre | dep) * cs), pack_h(bf_lo(pcim | dep) * cs, bf_hi(pcim | dep) * cs)};
  const H2 z1 = hpack(v); SQ(v)
  const H2 z2 = hpack(v); SQ(v)
  const H2 z4 = hpack(v); SQC(v)
  const H2 w1 = hpack(v); SQ(v)
  const H2 w2 = hpack(v); SQ(v)
  const H2 w4 = hpack(v);
  const H2 y64 = hpack(u); SQC(u) SQ(u)
  const H2 z256 = hpack(u); SQ(u)
  const H2 z512 = hpack(u); SQ(u)
  const H2 z1024 = hpack(u);
#define ST(k, h, a, c) sts128((ta ^ ((k) << 4)) + (h) * 128, a.x, a.y, c.x, c.y);
  const H2 one = {0x3c003c00u, 0u};
  const H2 c1 = hmul(cc, z1), c2 = hmul(cc, z2), c3 = hmul(c1, z2), c4 = hmul(cc, z4), w3 = hmul(w1, w2);
  ST(0, 0, one, c1) ST(1, 0, w1, c2) ST(2, 0, w2, c3) ST(3, 0, w3, c4)
  const H2 c5 = hmul(c1, z4), c6 = hmul(c2, z4), c7 = hmul(c3, z4), c8 = hmul(c4, z4);
  const H2 w5 = hmul(w4, w1), w6 = hmul(w4, w2), w7 = hmul(w4, w3);
  ST(4, 0, w4, c5) ST(5, 0, w5, c6) ST(6, 0, w6, c7) ST(7, 0, w7, c8)
  const H2 d0 = hmul(c2, z256), d1 = hmul(c4, z256), d2 = hmul(c6, z256), d3 = hmul(c8, z256);
  const H2 d4 = hmul(c4, z512), d5 = hmul(c8, z512), d6 = hmul(d1, z512), d7 = hmul(d3, z512);
  const H2 f0 = hmul(c8, z1024), f1 = hmul(d3, z1024), f2 = hmul(d5, z1024), f3 = hmul(d7, z1024);
  ST(0, 1, d0, f0) ST(1, 1, d1, f1) ST(2, 1, d2, f2) ST(3, 1, d3, f3) ST(4, 1, d4, cc) ST(7, 1, d7, y64)
  sts64((ta ^ (5 << 4)) + 128, d5.x, d5.y);
  sts64((ta ^ (6 << 4)) + 128, d6.x, d6.y);
  __syncwarp();
#pragma unroll 1
  for (int s = 0; s < 8 / UNR; s++) {
#pragma unroll
    for (int z = 0; z < ((ABL & 64) ? UNR / 2 : UNR); z++) {
      const uint4 e1 = lds128((ca ^ ((z & 1) << 4)) + z * 1024), e2 = lds128((ca ^ ((z & 1) << 4)) + z * 1024 + 128);
      const uint2 yv = lds64((cf ^ ((z & 1) << 4)) + z * 1024);
      const H2 y = {yv.x, yv.y}, a0 = {e1.x | zero, e1.y | zero}, a1 = hmul(a0, y), a2 = hmul(a1, y), a3 = hmul(a2, y);
      mma_f16(ka[0], a0.x, a1.x, a0.y, a1.y, e1.z, e1.w);
      mma_f16(ka[1], a0.x, a1.x, a0.y, a1.y, e2.x, e2.y);
      mma_f16(ka[2], a0.x, a1.x, a0.y, a1.y, e2.z, e2.w);
      mma_f16(ka[3], a2.x, a3.x, a2.y, a3.y, e1.z, e1.w);
      mma_f16(ka[4], a2.x, a3.x, a2.y, a3.y, e2.x, e2.y);
      mma_f16(ka[5], a2.x, a3.x, a2.y, a3.y, e2.z, e2.w);
    }
    ca += UNR * 1024; cf += UNR * 1024;
  }
  if (nb) bar_arrive(nb, 160);
#pragma unroll
  for (int q = 0; q < 4; q++) {
    const int m = 3 * (q >> 1), o = 2 * (q & 1);
    pk[3 * q] = pack_bf(ka[m][o + 1] * unscale, ka[m][o] * unscale);
    pk[3 * q + 1] = pack_bf(ka[m + 1][o + 1] * unscale, ka[m + 1][o] * unscale);
    pk[3 * q + 2] = pack_bf(ka[m + 2][o] * unscale, ka[m + 2][o + 1] * unscale);
  }
}
struct TapAddr { uint32_t w, c, pa, pb, pc, pd, px, sel; };
__device__ __forceinline__ TapAddr tap_addr(uint32_t reg, int wq, int lane) {
  const int g = lane >> 2, t = lane & 3, r = 8 * wq + g;
  TapAddr a;
  a.w = reg + R_KTAB + lane * 8;
  a.c = reg + R_KTAB + 4096 + lane * 4;
  a.pa = reg + R_P + (17 + 8 * r + 2 * t) * 4;
  a.pb = reg + R_P + (274 + 8 * r + 4 * t) * 4;
  a.pc = t < 2 ? a.pb + 4 : reg + R_T53 + (32 * t - 48 + r) * 4;
  a.pd = reg + R_T97 + (8 + 32 * t + 16 * (g & 1) + (r >> 1)) * 8;
  a.px = (t & 1 ? r == 31 : 4 * r + t == 2) ? reg + R_P + (16 + (t == 2 ? 0 : (t == 3 ? 257 : 514))) * 4 : 0u;
  a.sel = (g & 1) ? 0x3276 : 0x5410;
  asm volatile("" : "+r"(a.w), "+r"(a.c), "+r"(a.pa), "+r"(a.pb), "+r"(a.pc), "+r"(a.pd), "+r"(a.px), "+r"(a.sel));
  return a;
}
__device__ __forceinline__ void put_partials(const uint32_t (&pk)[12], const TapAddr& a, int wq, int lane) {
#pragma unroll
  for (int q = 0; q < 4; q++) {
    sts64(a.w + wq * 256 + q * 1024, pk[3 * q], pk[3 * q + 1]);
    sts32(a.c + wq * 128 + q * 512, pk[3 * q + 2]);
  }
  sts64_if(lane < 9, a.w + R_P - R_KTAB, 0u, 0u);
}
__device__ __forceinline__ void build_taps(const TapAddr& a, uint32_t o, int wq, int lane, uint32_t dskip) {
  const bool lo = (lane & 2) == 0;
  uint2 v[4];
  uint32_t u[4];
#pragma unroll
  for (int w = 0; w < 4; w++) { v[w] = lds64(a.w + o + wq * 1024 + w * 256); u[w] = lds32(a.c + o + wq * 512 + w * 128); }
  const uint32_t wa = b2add(b2add(v[0].x, v[1].x), b2add(v[2].x, v[3].x)), wb = b2add(b2add(v[0].y, v[1].y), b2add(v[2].y, v[3].y));
  const uint32_t wc = b2add(b2add(u[0], u[1]), b2add(u[2], u[3])), dup = __byte_perm(wb, 0, 0x1010);
  const uint32_t vc = __byte_perm(wc, __shfl_xor_sync(~0u, wc, 4), a.sel);
  sts16(a.pa + o, wa >> 16); sts32(a.pa + o + 4, wa); sts16(a.pa + o + 10, wa);
  sts32(a.pc + o, wb);
  sts16_if(lo, a.pb + o, wb >> 16); sts64_if(lo, a.pb + o + 8, dup, dup); sts16_if(lo, a.pb + o + 18, wb);
  sts32_if(lo, a.pd + o, vc); sts32_if(lo, a.pd + o + 36, vc);
  const uint32_t sv = (lane & 1) ? (lo ? wb : wa) : b2add(wc, dskip);
  sts16_if(a.px, a.px + o, sv); sts16_if(a.px, a.px + o + 6, sv);
}
__device__ __forceinline__ void make_xq(uint32_t reg, uint32_t xq, int lane) {
  const int la = (lane >> 2) - 2 * (lane & 3);
  const uint32_t pl = reg + R_P + 64 + la * 4;
  const uint32_t r64 = lds32(pl + 64 * 32), r65 = lds32(pl + 65 * 32), r63 = lds32(pl + 63 * 32);
  const uint32_t kk = lds32(reg + R_T53 + 79 * 4);
  const uint32_t ra = __byte_perm(kk, 0, la == 3 ? 0x4410 : (la == 4 ? 0x1010 : (la == 5 ? 0x1044 : 0x4444)));
  const uint32_t rb = __byte_perm(kk, 0, la == -5 ? 0x4410 : (la == -4 ? 0x1010 : (la == -3 ? 0x1044 : 0x4444)));
  sts128(xq + lane * 16, r64, r65, r63, r64);
  sts128(xq + lane * 16 + 512, ra, rb, 0u, ra);
  sts128(xq + lane * 16 + 1024, rb, 0u, r65, 0u);
}

__global__ void __launch_bounds__(480, 1) helper_kernel(const __grid_constant__ Params p) {
  extern __shared__ __align__(1024) unsigned char smem_raw[];
  const int lane = threadIdx.x & 31, tt = threadIdx.x & 127, nh = p.nhelp;
  KIn in = kgen_load(p, 512 * min((int)(blockIdx.x + (threadIdx.x >> 7) * nh), kCTAs - 1) + 384 + tt, true);
  const int warp = __shfl_sync(~0u, (int)threadIdx.x >> 5, 0), wq = warp & 3, wg = warp < 12 ? warp >> 2 : wq;
  const uint32_t reg = (uint32_t)__cvta_generic_to_shared(smem_raw) + wg * HELP_WG;
  int b = blockIdx.x + wg * nh;
  if (warp >= 12) {
    for (; b < kCTAs; b += 3 * nh) {
      const uint32_t tag = __ldcg(&p.epoch[b]) + 1;
      bar_arrive(4 + wg, 160);
      bar_sync(7 + wg, 160);
      make_xq(reg, reg + R_END, lane);
      fence_async_smem();
      __syncwarp();
      if (elect()) {
        bulk_s2g(p.kt + b * KT_BYTES, reg + R_P, KT_BYTES);
        asm volatile("cp.async.bulk.commit_group;" ::: "memory");
        asm volatile("cp.async.bulk.wait_group 0;" ::: "memory");
      }
      __syncwarp();
      if (lane < 2) st_flag(&p.kflag[8 * b + 4 * lane], tag);
    }
    return;
  }
  const TapAddr ta = tap_addr(reg, wq, lane);
  while (b < kCTAs) {
    const int bn = b + 3 * nh;
    const KIn nx = kgen_load(p, 512 * (bn < kCTAs ? bn : b) + 384 + tt, true);
    const uint32_t dsk = ld16(p.adsk + 4 * b + 3);
    uint32_t pk[12];
    kgen<8>(in, reg + 20480 + wq * 8192, lane, p.zero, pk);
    bar_sync(4 + wg, 160);
    stsz_if(tt < 68, reg + R_T53 - 64 + tt * 16);
    put_partials(pk, ta, wq, lane);
    bar_sync(1 + wg, 128);
    build_taps(ta, 0, wq, lane, dsk);
    fence_async_smem();
    bar_arrive(7 + wg, 160);
    b = bn; in = nx;
  }
  uint32_t* ep = &p.epoch[kCTAs + blockIdx.x * 12 + warp];
  const uint32_t tag = __ldcg(ep) + 1;
  uint32_t w[7];
#pragma unroll
  for (int k = 0; k < 7; k++) w[k] = __ldg((const uint32_t*)p.sv[4] + 32 * k + lane);
#pragma unroll 1
  for (int q = (11 - warp) * nh + nh - 1 - blockIdx.x; q < 512; q += 12 * nh) {
    float sm[4];
#pragma unroll
    for (int r = 0; r < 4; r++) {
      uint32_t v[7];
#pragma unroll
      for (int k = 0; k < 7; k++) v[k] = __ldg(p.x + (4 * q + r) * 224 + 32 * k + lane);
      sm[r] = 0.f;
#pragma unroll
      for (int k = 0; k < 7; k++) {
        uint32_t m;
        asm("mul.rn.bf16x2 %0, %1, %2;" : "=r"(m) : "r"(v[k]), "r"(w[k]));
        sm[r] += bf_lo(m) + bf_hi(m);
      }
    }
    const bool o1 = lane & 1, o2 = lane & 2;
    const float a0 = (o1 ? sm[1] : sm[0]) + __shfl_xor_sync(~0u, o1 ? sm[0] : sm[1], 1);
    const float a1 = (o1 ? sm[3] : sm[2]) + __shfl_xor_sync(~0u, o1 ? sm[2] : sm[3], 1);
    float sg = (o2 ? a1 : a0) + __shfl_xor_sync(~0u, o2 ? a0 : a1, 2);
#pragma unroll
    for (int o = 4; o < 32; o <<= 1) sg += __shfl_xor_sync(~0u, sg, o);
    const float gv = bf_round(__fdividef(1.0f, 1.0f + __expf(-bf_round(sg))));
    if (lane < 4) asm volatile("st.relaxed.gpu.global.v2.u32 [%0], {%1,%2};" ::"l"(&p.gate[4 * q + lane]), "r"(pack_bf(gv, 1.0f - gv)), "r"(tag) : "memory");
  }
  if (lane == 0) *ep = tag;
}

template <int CS>
__global__ void __launch_bounds__(512, 1)
fused_kernel(const __grid_constant__ Params p, const __grid_constant__ Maps tm) {
  asm volatile("griddepcontrol.launch_dependents;" ::: "memory");
  const KIn kin = kgen_load(p, 512 * blockIdx.x + ((threadIdx.x + 256) & 511), (threadIdx.x >> 7) != 1);
  const uint32_t c_start = clock32();
  extern __shared__ __align__(1024) unsigned char smem_raw[];
  const uint32_t sb = __shfl_sync(~0u, (uint32_t)__cvta_generic_to_shared(smem_raw), 0);
  const uint32_t bars = sb + OFF_MISC;
  const int tid = threadIdx.x, lane = tid & 31, g = lane >> 2, t = lane & 3;
  const int warp = __shfl_sync(~0u, tid >> 5, 0), wq = warp & 3;
  const int b = blockIdx.x;
  int ti, tj;
  if (CS == 8) { int c = b >> 1; tj = c % 7; ti = (c / 7) * 2 + (b & 1); }
  else { ti = b & 15; tj = b >> 4; }

  const int r8 = lane & 7, mi = lane >> 3;
  const int kch = ((warp >> 2) + 2) & 3;

  auto kcol = [&](int k) { return 64 * (k == 6 ? tj : (k == tj ? 6 : k)); };
  auto load_n = [&](int n) {
    const int k = n >> 1, isb = n & 1;
    tma5(sb + (n < 9 ? n : n - 9) * SLOT, &tm.m[isb], kcol(k), isb ? 8 * tj : 0, isb ? 0 : ti, bars + 8 * (B_STAGE + k));
  };
  auto load_c = [&](int st) {
    tma5(sb + (st < 4 ? st + 5 : (st == 4 ? 0 : st)) * SLOT, &tm.m[TM_C], kcol(st ? st - 1 : 6), 4 * tj, 0, bars + 8 * (st < 5 ? B_CEARLY : B_CLATE));
  };
  const uint32_t kreg = sb + OFF_REG + kch * REG_SZ;
  if (kch == 3) {
    if (elect()) {
#pragma unroll
      for (int z = 0; z < 8; z++)
        mbar_init(bars + 8 * (8 * wq + z), (wq == 0 ? 1 : (((wq == 1 ? 0x12222222u : (wq == 2 ? 0x18881181u : 0x81448484u)) >> (4 * z)) & 15)));
      mbar_init(bars + 8 * (32 + wq), wq < 2 ? 7 : 1);
      asm volatile("fence.mbarrier_init.release.cluster;" ::: "memory");
    }
    __syncwarp();
    asm volatile("barrier.cluster.arrive.relaxed.aligned;" ::: "memory");
    if (wq == 0 && lane < 8) mbar_expect(bars + 8 * lane, 2 * SLOT);
    if (elect()) {
      asm volatile("prefetch.tensormap [%0];" ::"l"(&tm.m[wq]) : "memory");
      if (wq == 0) asm volatile("prefetch.tensormap [%0];" ::"l"(&tm.m[TM_A]) : "memory");
      if (wq == 1) while (clock32() - c_start < UDELAY) {}
      if (wq == 1) {
        mbar_expect(bars + 8 * B_LAND, SLOT);
#pragma unroll 1
        for (int z = 0; z < 4; z++)
          tma5(sb + OFF_REG + z * REG_SZ + R_LAND, &tm.m[TM_U], 4 * CS * (b / CS), 0, (32 / CS) * (b % CS) + (8 / CS) * z, bars + 8 * B_LAND);
        asm volatile("cp.async.bulk.prefetch.L2.global [%0], 3584;" ::"l"(p.w[0] + b * 3584) : "memory");
        asm volatile("cp.async.bulk.prefetch.L2.global [%0], 3584;" ::"l"(p.w[1] + b * 3584) : "memory");
      }
      if (wq == 2) { mbar_expect(bars + 8 * B_UFULL, SLOT); mbar_expect(bars + 8 * B_CEARLY, 5 * SLOT); }
    }
    __syncwarp();
    const int tt = tid & 127, z = tid & 63;
    if (tt < 64) sts128(sb + OFF_REG + (tt >> 4) * REG_SZ + ((tt >> 3) & 1) * R_UHI + r8 * 16, 0u, 0u, 0u, 0u);
    if (tt < 68) st_flag(tt < 64 ? (uint32_t*)&p.agg[(tj * 16 + ti) * 64 + z] : &p.hflag[(ti * 8 + tj) * 16 + 4 * z], 0u);
    if (wq == 1) {
      if (lane < 8) asm volatile("cp.async.cg.shared.global [%0], [%1], 16;" ::"r"(sb + OFF_DSK + lane * 16), "l"(p.sv[3] + 64 * tj + 8 * lane) : "memory");
      if (lane < 3) asm volatile("cp.async.ca.shared.global [%0], [%1], 4;" ::"r"(sb + OFF_AD + lane * 4), "l"(lane < 2 ? (const void*)(p.adsk + 4 * b + 2 * lane) : (const void*)&p.epoch[b]) : "memory");
    }
    if (wq >= 2) {
      const float lre = bf_lo(ld16(p.sv[0] + 64 * tj + z)), lim = bf_lo(ld16(p.sv[1] + 64 * tj + z));
      const float dt = bf_round(expf(bf_lo(ld16(p.sv[2] + 64 * tj + z))));
      float sn, cs;
      sincospif(dt * lim * 0.3183098861837907f, &sn, &cs);
      const float mag = expf(dt * lre);
      const float lr = mag * cs, li = mag * sn;
      const float inv = __fdividef(2.0f, lre * lre + lim * lim);
      const float sr = ((lr - 1.0f) * lre + li * lim) * inv, si = (li * lre - (lr - 1.0f) * lim) * inv;
      const Cx mu = {lr, -li}, mu8 = csqr(csqr(csqr(mu))), mu32 = csqr(csqr(mu8)), mu64 = csqr(mu32), mu128 = csqr(mu64), mu256 = csqr(mu128);
      const Cx mu512 = csqr(mu256), mu96 = cmul(mu32, mu64), mu384 = cmul(mu128, mu256);
#define STC(o, a, c) sts128(sb + OFF_CST + (o), __float_as_uint(a.x), __float_as_uint(a.y), __float_as_uint(c.x), __float_as_uint(c.y));
      const Cx one = {1.f, 0.f}, mm = {p.bswap ? -si : sr, p.bswap ? sr : -si};
      STC(z * 64, one, one) STC(z * 64 + 16, mu32, mu128) STC(z * 64 + 32, mu64, mu256) STC(z * 64 + 48, mu96, mu384)
      STC(4096 + z * 16, mu, mm) STC(5120 + z * 16, mu8, mu512)
    }
    asm volatile("barrier.cluster.wait.aligned;" ::: "memory");
    mbar_wait0(bars + 8 * B_LAND);
    TS(12);
    if (wq >= 2 && elect()) asm volatile("cp.async.bulk.prefetch.L2.global [%0], 3584;" ::"l"(p.w[wq] + b * 3584) : "memory");
    uint32_t x[8][4];
#pragma unroll
    for (int q = 0; q < 8; q++) {
      const int v1 = q >> 2, hh = CS == 8 ? v1 : (q >> 1) & 1, oc = CS == 8 ? q & 3 : q & 1;
      ldsm4t(sb + OFF_REG + wq * REG_SZ + R_LAND + v1 * 2048 + (CS == 8 ? lane * 64 + ((oc ^ (r8 >> 1)) << 4) : hh * 1024 + lane * 32 + ((oc ^ (r8 >> 2)) << 4)),
             x[q][0], x[q][1], x[q][2], x[q][3]);
    }
    asm volatile("cp.async.wait_all;" ::: "memory");
    bar_arrive(1, 512);
    if (elect()) {
#pragma unroll 1
      for (int n = wq; n < 5; n += 4) load_n(n);
    }
    __syncwarp();
#pragma unroll
    for (int q = 0; q < 8; q++) {
      const int v1 = q >> 2, hh = CS == 8 ? v1 : (q >> 1) & 1, oc = CS == 8 ? q & 3 : q & 1;
      const int blk = CS == 8 ? 16 * (b & 7) + 4 * wq + t : 32 * (b & 3) + 8 * wq + 4 * v1 + t;
      uint32_t da, dbar;
      const uint32_t rank = 2 * oc + (g >> 2);
      asm("mapa.shared::cluster.u32 %0, %1, %2;" : "=r"(da) : "r"(sb + OFF_REG + (g & 3) * REG_SZ + (8 + blk) * 16 + hh * R_UHI), "r"(rank));
      asm("mapa.shared::cluster.u32 %0, %1, %2;" : "=r"(dbar) : "r"(bars + 8 * B_UFULL), "r"(rank));
      asm volatile("st.async.weak.shared::cluster.mbarrier::complete_tx::bytes.v4.b32 [%0], {%1,%2,%3,%4}, [%5];"
                   ::"r"(da), "r"(x[q][0]), "r"(x[q][1]), "r"(x[q][2]), "r"(x[q][3]), "r"(dbar) : "memory");
    }
    TS(15);
    if (wq < 2) {
      bar_sync(5 + wq, 160);
      if (elect()) {
#pragma unroll 1
        for (int n = 5 + 2 * wq; n < 7 + 2 * wq; n++) load_n(n);
        TX(13 - 12 * wq);
      }
      __syncwarp();
    }
  } else {
    uint32_t pk[12];
    asm volatile("barrier.cluster.arrive.relaxed.aligned;" ::: "memory");
    stsz_if((tid & 127) < 68, kreg + R_T53 - 64 + (tid & 127) * 16);
    const TapAddr ta = tap_addr(kreg, wq, lane);
    kgen<KUNR>(kin, warp < 8 ? sb + OFF_REG + wq * REG_SZ + R_KTAB : sb + OFF_TAB + (warp - 8) * 8192, lane, p.zero, pk, kch * KSTAG, kch < 2 ? 5 + kch : 0);
    TS4(3);
    bar_arrive(15, 512);
    bar_sync(1 + ((pk[0] & pk[1] & pk[2] & pk[3] & pk[4] & pk[5] & pk[6] & pk[7] & pk[8] & pk[9] & pk[10] & pk[11]) & p.zero), 512);
    put_partials(pk, ta, wq, lane);
    if (kch == 2) {
      bar_arrive(9, 256);
    } else {
      bar_sync(8 + kch, kch ? 256 : 128);
#pragma unroll 1
      for (int c = 0; c <= kch; c++) build_taps(ta, c * REG_SZ, wq, lane, lds16(sb + OFF_AD + 2 * (kch + c)));
    }
  }

  if (warp < 8) {
    const int wg = warp >> 2;
    const int sl = 8 * warp + g;
    float acc[64];
    auto fetch_kt = [&]() {
      if (elect()) {
        TX(5);
        asm volatile("fence.proxy.async.global;" ::: "memory");
        mbar_expect(bars + 8 * B_KT, KT_BYTES);
        bulk_g2s(sb + OFF_REG + 3 * REG_SZ + R_P, p.kt + b * KT_BYTES, R_END - R_P, bars + 8 * B_KT);
        bulk_g2s(sb + OFF_XQ, p.kt + b * KT_BYTES + R_END - R_P, 1536, bars + 8 * B_KT);
      }
      __syncwarp();
    };
    uint32_t kv = 0;
    const uint4* aggp = &p.agg[(tj * 16 + ti) * 64 + sl];
    asm volatile("" : "+l"(aggp));
    if (wg == 1) bar_sync(15, 512);
    {
      const uint64_t db = desc128(sb), da = db + wg * 512;
#pragma unroll
      for (int kc = 0; kc < 7; kc++) {
        TG(0, kc, 0);
        mbar_wait0(bars + 8 * (B_STAGE + kc));
        if (kc == 0) TS(0);
        if (kc == 3) TS(13);
        if (kc == 6) TS(14);
        TG(0, kc, 1);
        wg_fence();
#pragma unroll
        for (int ks = 0; ks < 4; ks++) wgmma_n128_ss(acc, da + ((2 * kc + 1) % 9) * 1024 + 2 * ks, db + ((2 * kc) % 9) * 1024 + 2 * ks, kc | ks);
        wg_commit();
        if (kc == 6 && CDEF && warp < 5) {
          mbar_wait0(bars + 8 * B_EMPTY4);
          if (elect()) load_c(warp);
          __syncwarp();
        }
        if ((kc >= 1 && kc < 4) || kc == 5) {
          wg_wait<1>();
          const uint32_t eb = bars + 8 * (kc < 4 ? B_EMPTY1 + kc - 1 : B_EMPTY4);
          if (elect()) mbar_arrive(eb);
          if (kc < 4 ? (wq == kc && 2 * kc + wg < 7) : (!CDEF && warp < 5)) {
            mbar_wait0(eb);
            if (elect()) {
              if (kc < 4) load_n(7 + 2 * kc + wg);
              else load_c(warp);
            }
            __syncwarp();
          }
          TG(0, kc, 3);
        }
      }
    }
    const uint32_t tag = lds32(sb + OFF_EP) + 1;
    const uint4 q0 = lds128(sb + OFF_CST + 4096 + sl * 16), q1 = lds128(sb + OFF_CST + 5120 + sl * 16), q2 = lds128(sb + OFF_CST + tid * 16);
    const uint2 q3 = lds64(sb + OFF_CST + sl * 64 + 16), q4 = lds64(sb + OFF_CST + sl * 64 + 32);
#define U2C(a, c) Cx{__uint_as_float(a), __uint_as_float(c)}
    const Cx mu = U2C(q0.x, q0.y), mu8 = U2C(q1.x, q1.y), mu512 = U2C(q1.z, q1.w), mu32t = U2C(q2.x, q2.y), mu128t = U2C(q2.z, q2.w);
    const Cx mu32 = U2C(q3.x, q3.y), mu64 = U2C(q4.x, q4.y);
    float m11 = __uint_as_float(q0.z), m12 = __uint_as_float(q0.w), m21 = p.bswap ? -m12 : m12, m22 = p.bswap ? m11 : -m11;
    wg_wait<0>();
    if (elect()) mbar_arrive(bars + 8 * B_G1DONE);
    TS(1);
    const Cx mr = {mu.x, p.bswap ? mu.y : -mu.y};
    Cx e[4];
#pragma unroll
    for (int c = 0; c < 4; c++) e[c] = {acc[16 * c], acc[16 * c + 2]};
#pragma unroll
    for (int k = 1; k < 8; k++) {
#pragma unroll
      for (int c = 0; c < 4; c++) {
        const int o = 16 * c + 4 * (k >> 1) + (k & 1);
        e[c] = cfma(mr, e[c], Cx{acc[o], acc[o + 2]});
      }
    }
#pragma unroll
    for (int c = 0; c < 4; c++) e[c] = {fmaf(m11, e[c].x, m12 * e[c].y), fmaf(m21, e[c].x, m22 * e[c].y)};
    Cx inc = cfma(mu8, cfma(mu8, cfma(mu8, e[0], e[1]), e[2]), e[3]);
    {
      Cx o = {__shfl_up_sync(~0u, inc.x, 1, 4), __shfl_up_sync(~0u, inc.y, 1, 4)};
      if (t >= 1) inc = cfma(mu32, o, inc);
      o = {__shfl_up_sync(~0u, inc.x, 2, 4), __shfl_up_sync(~0u, inc.y, 2, 4)};
      if (t >= 2) inc = cfma(mu64, o, inc);
    }
    asm volatile("{.reg .pred p; setp.eq.u32 p, %4, 3; @p st.relaxed.gpu.global.v4.u32 [%0], {%1,%2,%3,%2};}"
                 ::"l"(aggp), "r"(__float_as_uint(inc.x)), "r"(tag), "r"(__float_as_uint(inc.y)), "r"(t) : "memory");
    bar_arrive(NB_G1, 384);
    if (HOLD == 0) bar_arrive(NB_G1 + 2, 384);
    const uint32_t dep = clock32() & p.zero;
    Cx st = {__shfl_up_sync(~0u, inc.x, 1, 4), __shfl_up_sync(~0u, inc.y, 1, 4)};
    if (t == 0) st = {0.f, 0.f};
    TS(2);
    m11 = __uint_as_float(__float_as_uint(m11) | dep); m12 = __uint_as_float(__float_as_uint(m12) | dep);
    m21 = __uint_as_float(__float_as_uint(m21) | dep); m22 = __uint_as_float(__float_as_uint(m22) | dep);
#pragma unroll
    for (int k = 0; k < ((ABL & 1) ? 1 : 32); k++) {
      const int o = 4 * (k >> 1) + (k & 1);
      const float a = acc[o], c = acc[o + 2];
      acc[o] = fmaf(m11, a, m12 * c);
      acc[o + 2] = fmaf(m21, a, m22 * c);
    }
    if (HOLD == 2) bar_arrive(NB_G1 + 2 + (__float_as_uint(acc[63]) & p.zero), 384);
    {
      uint4 v[4];
      const uint4* src = aggp - 64 * (1 + t);
      const int nv = ti - t;
      uint32_t miss[4];
#pragma unroll
      for (int m = 0; m < 4; m++) { v[m] = make_uint4(0u, tag, 0u, tag); miss[m] = nv > 4 * m; }
      for (int it = 0; it < SPIN_MAX; it++) {
#pragma unroll
        for (int m = 0; m < 4; m++)
          asm volatile("{.reg .pred p; setp.ne.u32 p, %5, 0; @p ld.relaxed.gpu.global.v4.u32 {%0,%1,%2,%3}, [%4];}"
                       : "+r"(v[m].x), "+r"(v[m].y), "+r"(v[m].z), "+r"(v[m].w) : "l"(src - 256 * m), "r"(REPOLL ? miss[m] : (uint32_t)(nv > 4 * m)) : "memory");
#pragma unroll
        for (int m = 0; m < 4; m++) miss[m] = (v[m].y ^ tag) | (v[m].w ^ tag);
        if (!__any_sync(~0u, miss[0] | miss[1] | miss[2] | miss[3])) break;
      }
      if (HOLD == 3) bar_arrive(NB_G1 + 2, 384);
      Cx h = {__uint_as_float(v[3].x), __uint_as_float(v[3].z)};
#pragma unroll
      for (int m = 2; m >= 0; m--) h = cfma(mu512, h, Cx{__uint_as_float(v[m].x), __uint_as_float(v[m].z)});
      h = cmul(h, mu128t);
      h.x += __shfl_xor_sync(~0u, h.x, 1); h.y += __shfl_xor_sync(~0u, h.y, 1);
      h.x += __shfl_xor_sync(~0u, h.x, 2); h.y += __shfl_xor_sync(~0u, h.y, 2);
      st = cfma(mu32t, h, st);
    }
    TS(3);
    mbar_wait0(bars + 8 * B_G1DONE);
    if (warp == 7) asm volatile("ld.relaxed.gpu.global.u32 %0, [%1];" : "=r"(kv) : "l"(&p.kflag[8 * b]) : "memory");
    {
      const uint32_t hw = sb + SLOT + warp * 2048, hrow = hw + ((mi & 1) ^ p.cswap) * 1024 + r8 * 128;
#pragma unroll
      for (int nh = 0; nh < 2; nh++) {
        Cx s0 = st, s1 = cfma(mu8, st, e[2 * nh]);
        if (nh == 0) st = cfma(mu8, s1, e[1]);
#pragma unroll
        for (int q = 0; q < 2; q++) {
          uint32_t pk0[4], pk1[4];
#pragma unroll
          for (int z = 0; z < 2; z++) {
            const int o = 32 * nh + 8 * q + 4 * z;
            Cx a = cfma(mu, s0, Cx{acc[o], acc[o + 2]});
            s0 = cfma(mu, a, Cx{acc[o + 1], acc[o + 3]});
            pk0[2 * z] = pack_bf(a.x, s0.x); pk0[2 * z + 1] = pack_bf(a.y, s0.y);
            a = cfma(mu, s1, Cx{acc[16 + o], acc[18 + o]});
            s1 = cfma(mu, a, Cx{acc[17 + o], acc[19 + o]});
            pk1[2 * z] = pack_bf(a.x, s1.x); pk1[2 * z + 1] = pack_bf(a.y, s1.y);
          }
          const uint32_t ad = hrow + nh * SLOT + (((2 * q + (mi >> 1)) ^ r8) << 4);
          stsm4(ad, pk0[0], pk0[1], pk0[2], pk0[3]);
          stsm4(ad ^ 64, pk1[0], pk1[1], pk1[2], pk1[3]);
        }
        if (nh == 1 && HOLD == 1) bar_arrive(NB_G1 + 2, 384);
        fence_async_smem();
        __syncwarp();
        if (elect()) {
          bulk_s2g(&p.h[(ti * 7 + tj) * 2048 + nh * 1024 + warp * 128], hw + nh * SLOT, 2048);
          asm volatile("cp.async.bulk.commit_group;" ::: "memory");
        }
        __syncwarp();
        if (nh == 0) st.x = __uint_as_float(__float_as_uint(st.x) | (clock32() & p.zero));
      }
    }
    TS(4);
    auto await_h = [&]() {
      if (elect()) {
        asm volatile("cp.async.bulk.wait_group 1;" ::: "memory");
        mbar_arrive(bars + 8 * B_HST);
        asm volatile("cp.async.bulk.wait_group 0;" ::: "memory");
        mbar_arrive(bars + 8 * (B_HST + 1));
      }
      __syncwarp();
    };
    if (wg == 1) {
      const bool kt_early = __all_sync(~0u, kv == tag);
      if (kt_early) fetch_kt();
      if (wq == 0) {
        uint32_t* fl = &p.hflag[(ti * 8 + tj) * 16 + 4 * lane];
#pragma unroll 1
        for (int z = 0; z < 2; z++) {
          if (elect()) {
            if (z == 0) asm volatile("cp.async.bulk.wait_group 1;" ::: "memory");
            else asm volatile("cp.async.bulk.wait_group 0;" ::: "memory");
          }
          __syncwarp();
          mbar_wait0(bars + 8 * (B_HST + z));
          if (lane < 2) st_flag(fl + 8 * z, tag);
          if (lane == 0) TX(2 + z);
        }
        if (elect()) mbar_arrive(bars + 8 * B_HOUT);
#pragma unroll 1
        for (int z = 0; z < 2; z++) {
          mbar_wait0(bars + 8 * (B_STEP0 + 2 * z));
          if (elect()) load_c(5 + z);
          __syncwarp();
        }
      } else if (await_h(), wq < 3) {
        const int nh = wq - 1;
        const uint32_t* fl = &p.hflag[(ti * 8 + r8) * 16 + 8 * nh];
        uint32_t ready = 0;
#pragma unroll 1
        for (int s = 0; s < 6; s++) {
          const int jp = s == tj ? 6 : s;
          const uint32_t dst = sb + ((s & 1) ? OFF_REG + ((s & 2) + nh) * REG_SZ : (3 - (s & 2) + nh) * SLOT), fb = bars + 8 * (B_FULLH + s);
          for (int it = 0; !((ready >> jp) & 1) && it < SPIN_MAX; it++) {
            uint32_t v = 0;
            if (!HONE || (lane < 7 && !((ready >> lane) & 1))) asm volatile("ld.acquire.gpu.global.u32 %0, [%1];" : "=r"(v) : "l"(fl) : "memory");
            ready |= __ballot_sync(~0u, v == tag);
          }
          mbar_wait0(bars + 8 * (B_XFREE + s));
          if (elect()) {
            asm volatile("fence.proxy.async.global;" ::: "memory");
            mbar_expect(fb, SLOT);
            bulk_g2s(dst, &p.h[(ti * 7 + jp) * 2048 + nh * 1024], SLOT, fb);
          }
          __syncwarp();
        }
      } else {
        if (!kt_early) {
          int kit = 0;
          do { asm volatile("ld.acquire.gpu.global.u32 %0, [%1];" : "=r"(kv) : "l"(&p.kflag[8 * b]) : "memory"); } while (!__all_sync(~0u, kv == tag) && ++kit < SPIN_MAX);
          fetch_kt();
        }
#pragma unroll
        for (int z = 0; z < 8; z++) sts128(sb + OFF_GF + z * 512 + lane * 16, 0u, 0u, 0u, 0u);
        __syncwarp();
        uint4 v[2];
        mbar_wait0(bars + 8 * (GLATE ? B_REGFREE2 : B_STEP0));
        for (int it = 0; it < SPIN_MAX; it++) {
#pragma unroll
          for (int k = 0; k < 2; k++)
            asm volatile("ld.relaxed.gpu.global.v4.u32 {%0,%1,%2,%3}, [%4];" : "=r"(v[k].x), "=r"(v[k].y), "=r"(v[k].z), "=r"(v[k].w) : "l"(&p.gate[128 * ti + 4 * lane + 2 * k]) : "memory");
          if (__all_sync(~0u, v[0].y == tag && v[0].w == tag && v[1].y == tag && v[1].w == tag)) break;
          __nanosleep(100);
        }
        if (lane == 0) TX(12);
        sts128(sb + OFF_OMG + ((g & 1) * 64 + mi * 16 + 4 * t) * 4, v[0].x & 0xffff0000u, v[0].z & 0xffff0000u, v[1].x & 0xffff0000u, v[1].z & 0xffff0000u);
        const uint32_t ga = sb + OFF_GF + (g & 1) * 2048 + (lane & 1) * 1024 + 9 * mi * 16 + (lane & 2) * 5;
        sts16(ga, v[0].x); sts16(ga + 68, v[0].z); sts16(ga + 512, v[1].x); sts16(ga + 580, v[1].z);
        __syncwarp();
        if (elect()) mbar_arrive(bars + 8 * B_GATE);
      }
      return;
    }

    {
      const uint32_t dsk = lds32(sb + OFF_DSK + 32 * wq + 4 * g);
      const uint32_t dl = dsk & 0xffffu, dh = dsk & 0xffff0000u;
      const uint32_t a0 = g == t ? dl : 0u, a1 = g == t ? dh : 0u, a2 = g == t + 4 ? dl : 0u, a3 = g == t + 4 ? dh : 0u;
      const uint32_t xa = sb + 3 * SLOT + (8 * (mi >> 1) + r8) * 128 + (((2 * wq + (mi & 1)) ^ r8) << 4);
#pragma unroll
      for (int q = 0; q < ((ABL & 2) ? 1 : 8); q++) {
        uint32_t x0, x1, x2, x3;
        ldsm4(xa + q * 2048, x0, x1, x2, x3);
        mma_bf16_z(&acc[8 * q], a0, a1, a2, a3, x0, x1);
        mma_bf16_z(&acc[8 * q + 4], a0, a1, a2, a3, x2, x3);
      }
    }
    if (elect()) mbar_arrive(bars + 8 * B_XFREE);
    TS(5);
    await_h();
    mbar_wait0(bars + 8 * B_HOUT);
    mbar_wait0(bars + 8 * B_CEARLY);
    {
      uint64_t da = desc128(sb + 5 * SLOT);
      const uint64_t ds = desc128(sb + 3 * SLOT) + (1023ull << 16) + (64ull << 32), dr = desc128(sb + OFF_REG) + ((uint64_t)(REG_SZ / 16 - 1) << 16) + (64ull << 32);
      uint64_t db = ds - 2048;
#pragma unroll 1
      for (int s = 0; s < 7; s++) {
        TG(1, s, 0);
        wg_fence();
#pragma unroll
        for (int ks = 0; ks < 8; ks++) wgmma_n128_ss_tb(acc, da + (ks >> 2) * 512 + (ks & 3) * 2, db + (ks >> 2) * 64 + (ks & 3) * 256);
        wg_commit();
        if (s == 6) break;
        if (s == 0) wg_wait<0>();
        else wg_wait<1>();
        if (s < 4 && s != 1 && elect()) mbar_arrive(bars + 8 * (B_STEP0 + s));
        db = (s & 1) ? dr + (s & 2) * (REG_SZ / 16) : ds - (s & 2) * 1024;
        da += s == 3 ? -8192 : (s == 4 ? 5120 : 1024);
        if (s == 4) mbar_wait0(bars + 8 * B_CLATE);
        if (s == 0) TS(6);
        TG(1, s, 3);
        mbar_wait0(bars + 8 * (B_FULLH + s));
        if (s == 0) bar_sync(NB_CONV, 384);
      }
    }
    TS(7);
    mbar_wait0(bars + 8 * B_GATE);
    float2* op = (float2*)(p.out + (128 * ti + 32 * t) * 448 + 64 * tj + 16 * wq + 2 * g);
#pragma unroll
    for (int nh = 0; nh < 2; nh++) {
      uint4 gf[4];
      uint32_t af[4][4];
#pragma unroll
      for (int k = 0; k < 4; k++) gf[k] = lds128(sb + OFF_GF + nh * 2048 + k * 512 + lane * 16);
      if (nh == 0) { mbar_wait0(bars + 8 * B_FULLA); TS(8); }
      const uint32_t ab = sb + 7 * SLOT + nh * 8192 + (16 * wq + 2 * r8 + (mi & 1)) * 128;
#pragma unroll
      for (int k = 0; k < 4; k++) ldsm4(ab + (((2 * k + (mi >> 1)) ^ r8) << 4), af[k][0], af[k][1], af[k][2], af[k][3]);
      if (nh == 0) { wg_wait<0>(); TS(9); }
#pragma unroll
      for (int jp = 0; jp < 4; jp++) {
        const uint4 om = lds128(sb + OFF_OMG + (nh * 64 + t * 16 + 4 * jp) * 4);
#pragma unroll
        for (int z = 0; z < 2; z++) {
          const int jj = 2 * jp + z, k = jj & 3;
          float ga[4];
          mma_bf16_z(ga, af[k][0], af[k][1], af[k][2], af[k][3], jj < 4 ? gf[k].x : gf[k].z, jj < 4 ? gf[k].y : gf[k].w);
          const float o0 = __uint_as_float(z ? om.z : om.x), o1 = __uint_as_float(z ? om.w : om.y);
          op[(16 * nh + 2 * jj) * 224] = make_float2(fmaf(o0, acc[32 * nh + 4 * jj], ga[0]), fmaf(o0, acc[32 * nh + 4 * jj + 2], ga[2]));
          op[(16 * nh + 2 * jj + 1) * 224] = make_float2(fmaf(o1, acc[32 * nh + 4 * jj + 1], ga[1]), fmaf(o1, acc[32 * nh + 4 * jj + 3], ga[3]));
        }
      }
    }
    if (tid == 0) p.epoch[b] = tag;
    TS(11);
  } else {
    const int team = kch, tt = tid & 127;
    asm volatile("{.reg .pred p, q; .reg .u32 n; mov.u32 n, 0;\n"
                 "W: mbarrier.try_wait.parity.acquire.cluster.shared::cta.b64 p, [%0], 0;\n"
                 "add.u32 n, n, 1; setp.lt.and.u32 q, n, 1048576, !p; @q bra W;}" ::"r"(bars + 8 * B_UFULL) : "memory");
    bar_sync(2 + team, 128);
    TS(13);
    const int la = g - 2 * t;
    const int pc = wq < 2 ? team : 3 - team, np = NP3 ? (team ? 3 : 1) : 2;
    const uint32_t preg = sb + OFF_REG + pc * REG_SZ;
    if ((wq & 1) == 0) {
      if (pc != 3) make_xq(preg, sb + OFF_XQ + (3 - pc) * 1536, lane);
      stsz_if(lane < 2, preg + R_A5 + HI_B - 16 + lane * (R_A3 - R_A5));
    }
#pragma unroll 1
    for (int ps = (ABL & 32) ? np : 0; ps <= np; ps++) {
      const uint32_t rg = ps < np ? sb + OFF_REG + (team ? 1 + ps : 3 * ps) * REG_SZ + (tt >> 1) * 16 : preg + 1024 + ((tt & 63) >> 1) * 16;
      const uint32_t same = rg + (lane & 1) * R_UHI + 128, oth = rg + ((lane & 1) ? 128 : R_UHI + 112);
      const uint4 c1 = lds128(same - 16), c2 = lds128(oth), c3 = lds128(same);
      uint32_t E[15] = {0u, 0u, 0u, 0u, c1.x, c1.y, c1.z, c1.w, c2.x, c2.y, c2.z, c2.w, c3.x, c3.y, c3.z};
      uint32_t O[14], Q[14], QQ[11], a5[4];
#pragma unroll
      for (int k = 7; k < 14; k++) { O[k] = __byte_perm(E[k], E[k + 1], 0x5432); Q[k] = b2add(E[k], O[k]); }
#pragma unroll
      for (int k = 7; k < 11; k++) QQ[k] = b2add(Q[k], Q[k + 1]);
#pragma unroll
      for (int w = 0; w < 4; w++) a5[w] = b2add(QQ[7 + w], E[9 + w]);
      const uint32_t ob = rg + (lane & 1) * HI_B, os = rg + (lane & 1) * HI_S;
      sts128(ob + R_A5, a5[0], a5[1], a5[2], a5[3]);
      sts128(ob + R_A3, b2add(O[9], Q[10]), b2add(O[10], Q[11]), b2add(O[11], Q[12]), b2add(O[12], Q[13]));
      if (ps < np) {
        const uint2 c0 = lds64(oth - 8);
        E[2] = c0.x; E[3] = c0.y;
#pragma unroll
        for (int k = 2; k < 7; k++) { O[k] = __byte_perm(E[k], E[k + 1], 0x5432); Q[k] = b2add(E[k], O[k]); }
#pragma unroll
        for (int k = 2; k < 7; k++) QQ[k] = b2add(Q[k], Q[k + 1]);
#define S9(w) b2add(b2add(QQ[2 + w], E[6 + w]), QQ[4 + w])
#define S7(w) b2add(b2add(O[6 + w], O[9 + w]), a5[w])
        sts128(os + R_A9, S9(0), S9(1), S9(2), S9(3));
        sts128(os + R_A7, S7(0), S7(1), S7(2), S7(3));
      }
    }
    fence_async_smem();
    bar_arrive(7 + 3 * team, 256);
    TS(9);

    const int rw = team ? 3 - wq : wq;
#pragma unroll 1
    for (int r = 0; r < 2; r++) {
      const uint32_t reg = sb + OFF_REG + (2 * r + team) * REG_SZ;
      if (r == 1) bar_sync(10 - 3 * team, 256);
      if (r == 1) TS(0);
      if (r + team == 2) mbar_wait0(bars + 8 * B_KT);
      if (r == 1) TS(1);
      float d[64];
      {
        uint32_t R[17];
#pragma unroll
        for (int k = 0; k < 17; k++) R[k] = lds32(reg + R_P + 64 + la * 4 + rw * 512 + (k - 1) * 32);
        const uint64_t db = (8ull << 32) | (uint64_t)((((reg + R_ULO + 128) & 0x3FFFFu) >> 4) | (((R_UHI - R_ULO) >> 4) << 16));
        if (r == 0) {
          bar_sync(NB_G1 + 2 * team, 384);
          if (HOLD == 0 && TDEL && team) {
            if (wq == 0) {
              const uint32_t c0 = clock32();
              uint32_t dly = 0;
              while (clock32() - c0 < TDEL + dly) dly = lds32(sb + OFF_EP) & p.zero;
            }
            bar_sync(3, 128);
          }
        }
        wg_fence();
#pragma unroll
        for (int s = 0; s < ((ABL & 8) ? 4 : 8); s++) wgmma_n128_rs(d, R[2 * s + 1], R[2 * s + 2], R[2 * s], R[2 * s + 1], db - s, s);
        wg_commit();
      }
      if (r == 1) {
        if (elect()) {
          asm volatile("cp.async.bulk.wait_group.read 0;" ::: "memory");
          mbar_arrive(bars + 8 * B_REGFREE);
        }
        __syncwarp();
      }
      wg_wait<0>();
      TS(5 + r);
      {
        const uint32_t xq = sb + OFF_XQ + (3 - 2 * r - team) * 1536 + lane * 16;
        const uint4 q32 = lds128(xq), q64 = lds128(xq + 512), q33 = lds128(xq + 1024);
        const uint32_t ua = reg + (8 * rw + r8) * 16 + 128 + (mi == 0 ? R_ULO : (mi == 1 ? R_UHI : (mi == 2 ? R_UHI - 16 - 512 : R_UHI - 16)));
#pragma unroll
        for (int h = 0; h < 3; h++) {
          uint32_t ul, uh, up, us;
          ldsm4((h == 0 && mi == 2) ? reg + r8 * 16 : ua + h * 512, ul, uh, up, us);
          mma_bf16(&d[4 * (4 * h + 4)], q32.x, q32.y, q32.z, q32.w, ul, uh);
          if (h < 2) mma_bf16(&d[4 * (4 * h + 8)], q64.x, q64.y, q64.z, q64.w, ul, uh);
          mma_bf16(&d[4 * (4 * h + 4)], q33.x, q33.y, q33.z, q33.w, up, us);
        }
      }
#define LIVE(n) (!SKIPD || (n) < 13 || (n) + rw < 16)
      const uint32_t tl = reg + (g - t) * 8, rowo = reg + (8 * rw + (r8 >> 1)) * 16;
      {
        uint2 T[10];
#pragma unroll
        for (int k = 0; k < 10; k++) T[k] = lds64(tl + R_T53 + (4 + 4 * k) * 8);
        const uint32_t a4 = rowo + R_A5 + (lane & 1) * (R_A3 - R_A5) + (mi == 1 ? HI_B : (mi == 2 ? HI_B - 16 : 0));
#pragma unroll
        for (int h = 0; h < ((ABL & 4) ? 1 : 6); h++) {
          uint32_t x[4];
          ldsm4t(a4 + (h >> 1) * 512 + (h & 1) * 64, x[0], x[1], x[2], x[3]);
#pragma unroll
          for (int k = 0; k < 5; k++)
            if (4 * (h >> 1) + 4 + k < 16) mma_bf16_if(LIVE(4 * (h >> 1) + 4 + k), &d[4 * ((4 * (h >> 1) + 4 + k) & 15)], x, T[2 * k + 1 - (h & 1)]);
        }
      }
      {
        const uint32_t a4 = rowo + R_A7 - (lane & 1) * (R_A7 - R_A9) + (mi >> 1) * 64 + (mi & 1) * HI_S;
        uint32_t x0[4], x1[4];
        ldsm4t(a4, x0[0], x0[1], x0[2], x0[3]);
        ldsm4t(a4 + 512, x1[0], x1[1], x1[2], x1[3]);
#pragma unroll
        for (int k = 0; k < ((ABL & 4) ? 1 : 8); k++) {
          const uint2 tv = lds64(tl + R_T97 + (8 + 8 * k) * 8);
          mma_bf16_if(LIVE(8 + k), &d[4 * (8 + k)], x0, tv);
          if (k < 4) mma_bf16_if(LIVE(12 + k), &d[4 * ((12 + k) & 15)], x1, tv);
        }
      }
      bar_sync(2 + team, 128);
      TS(7 + r);
#define PK(n) pack_bf(d[4 * (n)], d[4 * (n) + 2]), pack_bf(d[4 * (n) + 1], d[4 * (n) + 3])
#pragma unroll
      for (int c = 1; c < 4; c++) {
        const uint32_t a = reg + (c - 1) * 4096 + ((c + rw) & 3) * 1024 + lane * 16;
        if (c + rw < 4) { sts128(a, PK(c), PK(c + 4)); sts128(a + 512, PK(c + 8), PK(c + 12)); }
        else { sts128(a, 0u, 0u, PK(c)); sts128(a + 512, PK(c + 4), PK(c + 8)); }
      }
      bar_sync(2 + team, 128);
      const int oc = 4 * b + 2 * r + team;
      uint32_t res[8];
#pragma unroll
      for (int q = 0; q < 2; q++) {
        const uint32_t a = reg + rw * 1024 + q * 512 + lane * 16;
        const uint4 v0 = lds128(a), v1 = lds128(a + 4096), v2 = lds128(a + 8192);
        res[4 * q] = b2add(b2add(v0.x, v1.x), b2add(v2.x, pack_bf(d[32 * q], d[32 * q + 2])));
        res[4 * q + 1] = b2add(b2add(v0.y, v1.y), b2add(v2.y, pack_bf(d[32 * q + 1], d[32 * q + 3])));
        res[4 * q + 2] = b2add(b2add(v0.z, v1.z), b2add(v2.z, pack_bf(d[32 * q + 16], d[32 * q + 18])));
        res[4 * q + 3] = b2add(b2add(v0.w, v1.w), b2add(v2.w, pack_bf(d[32 * q + 17], d[32 * q + 19])));
      }
      const uint32_t st = reg + 12288 + rw * 1024, so = st + (lane ^ (((oc >> 1) & 7) << 2)) * 4;
#pragma unroll
      for (int q = 0; q < 8; q++) sts32(so + q * 128, res[q]);
      if (r == 1) bar_arrive(NB_CONV, 384);
      fence_async_smem();
      __syncwarp();
      if (elect()) {
        asm volatile("cp.async.bulk.tensor.4d.global.shared::cta.bulk_group [%0, {%4, %2, %3, %4}], [%1];" ::"l"(&tm.m[TM_A]), "r"(st), "r"(oc), "r"(2 * rw), "r"(0) : "memory");
        asm volatile("cp.async.bulk.commit_group;" ::: "memory");
      }
      __syncwarp();
      TS(11 + r);
    }
    if (elect()) {
      asm volatile("cp.async.bulk.wait_group 0;" ::: "memory");
      mbar_arrive(bars + 8 * B_REGFREE2);
    }
    if (warp == 8 && elect()) {
      const uint32_t want = 16 * (lds32(sb + OFF_EP) + 1);
      mbar_wait0(bars + 8 * B_REGFREE2);
      TX(8);
      asm volatile("red.relaxed.gpu.global.add.u32 [%0], 1;" ::"l"(&p.acnt[(b >> 4) * 32]) : "memory");
      mbar_expect(bars + 8 * B_FULLA, SLOT);
      if (AWAIT) mbar_wait0(bars + 8 * (B_STEP1 + AWAIT - 1));
      for (int it = 0; it < SPIN_MAX; it++) {
        uint32_t v;
        asm volatile("ld.acquire.gpu.global.u32 %0, [%1];" : "=r"(v) : "l"(&p.acnt[tj * 32]) : "memory");
        if ((int)(v - want) >= 0) break;
      }
      TX(10);
      asm volatile("fence.proxy.async.global;" ::: "memory");
      mbar_wait0(bars + 8 * (B_STEP1 + 1));
#pragma unroll 1
      for (int z = 0; z < 2; z++)
        bulk_g2s(sb + 7 * SLOT + z * 8192, &p.a[((ti * 2 + z) * 448 + 64 * tj) * 32], 8192, bars + 8 * B_FULLA);
    }
  }
}

typedef CUresult (*EncodeFn)(CUtensorMap*, CUtensorMapDataType, cuuint32_t, void*, const cuuint64_t*, const cuuint64_t*,
                             const cuuint32_t*, const cuuint32_t*, CUtensorMapInterleave, CUtensorMapSwizzle,
                             CUtensorMapL2promotion, CUtensorMapFloatOOBfill);

}

extern "C" void kernel_launch(void* const* d_in, const int* in_sizes, int n_in, void* d_out, int out_size) {
  (void)in_sizes; (void)n_in; (void)out_size;
  static EncodeFn encode = nullptr;
  static int cluster = 0, spare = 0;
  static Params p;
  static cudaStream_t side;
  static cudaEvent_t ev[2];
  cudaLaunchConfig_t cfg = {};
  cudaLaunchAttribute attr[2];
  cfg.gridDim = dim3(kCTAs);
  cfg.blockDim = dim3(512);
  cfg.dynamicSmemBytes = SMEM_TOTAL;
  cfg.stream = cudaStreamPerThread;
  cfg.attrs = attr;
  cfg.numAttrs = 1;
  attr[0].id = cudaLaunchAttributeClusterDimension;
  attr[0].val.clusterDim.y = 1;
  attr[0].val.clusterDim.z = 1;
  if (!encode) {
    void* fn = nullptr;
    cudaDriverEntryPointQueryResult qr;
    cudaGetDriverEntryPoint("cuTensorMapEncodeTiled", &fn, cudaEnableDefault, &qr);
    encode = (EncodeFn)fn;
    cudaStreamCreateWithFlags(&side, cudaStreamNonBlocking);
    cudaEventCreateWithFlags(&ev[0], cudaEventDisableTiming);
    cudaEventCreateWithFlags(&ev[1], cudaEventDisableTiming);
    cudaGetSymbolAddress((void**)&p.agg, g_agg);
    cudaGetSymbolAddress((void**)&p.h, g_h);
    cudaGetSymbolAddress((void**)&p.gate, g_gate);
    cudaGetSymbolAddress((void**)&p.a, g_a);
    cudaGetSymbolAddress((void**)&p.hflag, g_hflag);
    cudaGetSymbolAddress((void**)&p.acnt, g_acnt);
    cudaGetSymbolAddress((void**)&p.epoch, g_epoch);
    cudaGetSymbolAddress((void**)&p.kflag, g_kflag);
    cudaGetSymbolAddress((void**)&p.kt, g_kt);
    cudaFuncSetAttribute(helper_kernel, cudaFuncAttributeMaxDynamicSharedMemorySize, 3 * HELP_WG);
    cudaDeviceGetAttribute(&spare, cudaDevAttrMultiProcessorCount, 0);
    spare -= kCTAs;
    cudaFuncSetAttribute(fused_kernel<8>, cudaFuncAttributeMaxDynamicSharedMemorySize, SMEM_TOTAL);
    cudaFuncSetAttribute(fused_kernel<4>, cudaFuncAttributeMaxDynamicSharedMemorySize, SMEM_TOTAL);
    int n = 0;
    attr[0].val.clusterDim.x = 8;
    cluster = (cudaOccupancyMaxActiveClusters(&n, fused_kernel<8>, &cfg) == cudaSuccess && n * 8 >= kCTAs) ? 8 : 4;
    (void)cudaGetLastError();
  }
  attr[0].val.clusterDim.x = cluster;

  const cuuint32_t ones[5] = {1, 1, 1, 1, 1};
  Maps tm;
  {
    const cuuint64_t dim[5] = {448, 2, 4, 16, 16};
    const cuuint64_t str[4] = {896, 32 * 896, 2 * 896, 128 * 896};
    const cuuint32_t box[5] = {64, 2, 4, 16, 1};
    encode(&tm.m[TM_X], CU_TENSOR_MAP_DATA_TYPE_BFLOAT16, 5, d_in[0], dim, str, box, ones, CU_TENSOR_MAP_INTERLEAVE_NONE,
           CU_TENSOR_MAP_SWIZZLE_128B, CU_TENSOR_MAP_L2_PROMOTION_L2_128B, CU_TENSOR_MAP_FLOAT_OOB_FILL_NONE);
  }
  char* bre = (char*)d_in[10];
  char* bim = (char*)d_in[11];
  const int bswap = bim < bre;
  {
    const cuuint64_t dim[5] = {448, 8, 2, 56, 1};
    const cuuint64_t str[4] = {896, (cuuint64_t)(bswap ? bre - bim : bim - bre), 8 * 896, 448 * 896};
    const cuuint32_t box[5] = {64, 8, 2, 8, 1};
    encode(&tm.m[TM_B], CU_TENSOR_MAP_DATA_TYPE_BFLOAT16, 5, bswap ? bim : bre, dim, str, box, ones, CU_TENSOR_MAP_INTERLEAVE_NONE,
           CU_TENSOR_MAP_SWIZZLE_128B, CU_TENSOR_MAP_L2_PROMOTION_L2_128B, CU_TENSOR_MAP_FLOAT_OOB_FILL_NONE);
  }
  char* cre = (char*)d_in[12];
  char* cim = (char*)d_in[13];
  const int cswap = cim < cre;
  {
    const cuuint64_t dim[5] = {448, 8, 2, 28, 2};
    const cuuint64_t str[4] = {2 * 896, 896, 16 * 896, (cuuint64_t)(cswap ? cre - cim : cim - cre)};
    const cuuint32_t box[5] = {64, 8, 2, 4, 2};
    encode(&tm.m[TM_C], CU_TENSOR_MAP_DATA_TYPE_BFLOAT16, 5, cswap ? cim : cre, dim, str, box, ones, CU_TENSOR_MAP_INTERLEAVE_NONE,
           CU_TENSOR_MAP_SWIZZLE_128B, CU_TENSOR_MAP_L2_PROMOTION_L2_128B, CU_TENSOR_MAP_FLOAT_OOB_FILL_NONE);
  }
  {
    const cuuint64_t dim[5] = {448, 2, 4, 8, 32};
    const cuuint64_t str[4] = {896, 16 * 896, 2 * 896, 64 * 896};
    const cuuint32_t box[5] = {(cuuint32_t)(4 * cluster), 2, 4, 8, (cuuint32_t)(8 / cluster)};
    encode(&tm.m[TM_U], CU_TENSOR_MAP_DATA_TYPE_BFLOAT16, 5, d_in[0], dim, str, box, ones, CU_TENSOR_MAP_INTERLEAVE_NONE,
           cluster == 8 ? CU_TENSOR_MAP_SWIZZLE_64B : CU_TENSOR_MAP_SWIZZLE_32B, CU_TENSOR_MAP_L2_PROMOTION_L2_128B,
           CU_TENSOR_MAP_FLOAT_OOB_FILL_NONE);
  }
  {
    const cuuint64_t dim[4] = {32, 448, 8, 4};
    const cuuint64_t str[3] = {128, 448 * 128, 8 * 448 * 128};
    const cuuint32_t box[4] = {32, 1, 2, 4};
    encode(&tm.m[TM_A], CU_TENSOR_MAP_DATA_TYPE_UINT32, 4, p.a, dim, str, box, ones, CU_TENSOR_MAP_INTERLEAVE_NONE,
           CU_TENSOR_MAP_SWIZZLE_NONE, CU_TENSOR_MAP_L2_PROMOTION_NONE, CU_TENSOR_MAP_FLOAT_OOB_FILL_NONE);
  }
  p.w[0] = bre; p.w[1] = bim; p.w[2] = cre; p.w[3] = cim;
  p.zero = 0;
  p.x = (const uint32_t*)d_in[0];
  p.out = (float*)d_out;
  p.ap[0] = (const __nv_bfloat16*)d_in[1];
  p.ap[1] = (const __nv_bfloat16*)d_in[2];
  p.ap[2] = (const __nv_bfloat16*)d_in[3];
  p.ap[3] = (const __nv_bfloat16*)d_in[4];
  p.aldt = (const __nv_bfloat16*)d_in[5];
  p.adsk = (const __nv_bfloat16*)d_in[6];
  p.sv[0] = (const __nv_bfloat16*)d_in[8];
  p.sv[1] = (const __nv_bfloat16*)d_in[9];
  p.sv[2] = (const __nv_bfloat16*)d_in[14];
  p.sv[3] = (const __nv_bfloat16*)d_in[15];
  p.sv[4] = (const __nv_bfloat16*)d_in[16];
  p.bswap = bswap;
  p.cswap = cswap;
  cudaLaunchConfig_t hc = {};
  cudaLaunchAttribute ha[1];
  p.nhelp = spare >= 14 ? (spare < 38 ? spare : 38) : 38;
  hc.gridDim = dim3(p.nhelp);
  hc.blockDim = dim3(480);
  hc.dynamicSmemBytes = 3 * HELP_WG;
  hc.stream = cudaStreamPerThread;
  ha[0].id = cudaLaunchAttributeProgrammaticStreamSerialization;
  ha[0].val.programmaticStreamSerializationAllowed = 1;
  hc.attrs = ha;
  hc.numAttrs = 0;
  if (spare < 14) cudaLaunchKernelEx(&hc, helper_kernel, p);
  cudaStreamCaptureStatus cap = cudaStreamCaptureStatusNone;
  cudaStreamIsCapturing(cudaStreamPerThread, &cap);
  const bool fork = EVT && spare >= 14 && cap == cudaStreamCaptureStatusActive;
  if (fork) {
    attr[1].id = cudaLaunchAttributeProgrammaticEvent;
    attr[1].val.programmaticEvent.event = ev[0];
    attr[1].val.programmaticEvent.flags = 0;
    attr[1].val.programmaticEvent.triggerAtBlockStart = 1;
    cfg.numAttrs = 2;
  }
  if (cluster == 8) cudaLaunchKernelEx(&cfg, fused_kernel<8>, p, tm);
  else cudaLaunchKernelEx(&cfg, fused_kernel<4>, p, tm);
  if (fork) {
    cudaStreamWaitEvent(side, ev[0]);
    hc.stream = side;
    cudaLaunchKernelEx(&hc, helper_kernel, p);
    cudaEventRecord(ev[1], side);
    cudaStreamWaitEvent(cudaStreamPerThread, ev[1]);
  } else if (spare >= 14) {
    hc.numAttrs = 1;
    cudaLaunchKernelEx(&hc, helper_kernel, p);
  }
}
```
